```python
import torch

def _softmax(x, axis=-1):
    return torch.softmax(x, dim=axis)

def _gelu(x):
    return torch.nn.functional.gelu(x, approximate='tanh')

def _silu(x):
    return torch.nn.functional.silu(x)

def _sigmoid(x):
    return torch.sigmoid(x)

def _layernorm(x, axis=-1, eps=1e-05):
    m = x.mean(dim=axis, keepdim=True)
    v = x.var(dim=axis, keepdim=True, unbiased=False)
    return (x - m) / torch.sqrt(v + eps)

def _scatter_add(tgt, idx, src, axis=0):
    return tgt.clone().index_add_(axis, idx, src)

def _segment_sum(src, seg, n):
    out = torch.zeros((n,) + src.shape[1:], dtype=src.dtype)
    return out.index_add_(0, seg, src)

def _pad(x, pw):
    flat = tuple((v for pair in reversed(pw) for v in pair))
    return torch.nn.functional.pad(x, flat)
kernel_name = 'adaLN_cond__compressed_kv_cla__glu_gated_geglu__decode'

def setup_inputs():

    _w = lambda a: (lambda t: t.to(torch.bfloat16) if t.is_floating_point() else t)(torch.as_tensor(a))

    def _A_setup():
        B, H, Sq, Sk, D, M = (2, 32, 1, 8192, 128, 512)
        Dc = 4 * D
        return {'x': _w((lambda *s: torch.randn(*s, dtype=torch.bfloat16) * 0.05)(B, Sq, M)), 'c_kv': _w((lambda *s: torch.randn(*s, dtype=torch.bfloat16) * 3.2)(B, Sk, Dc)), 'w_q': _w((lambda *s: torch.randn(*s, dtype=torch.bfloat16) * 0.8)(M, H, D) * M ** (-0.5)), 'w_uk': _w((lambda *s: torch.randn(*s, dtype=torch.bfloat16) * 0.8)(Dc, H, D) * Dc ** (-0.5)), 'w_uv': _w((lambda *s: torch.randn(*s, dtype=torch.bfloat16) * 3.2)(Dc, H, D) * Dc ** (-0.5)), 'w_o': _w((lambda *s: torch.randn(*s, dtype=torch.bfloat16) * 3.2)(H, D, M) * (H * D) ** (-0.5))}
    _A_in = _A_setup()

    def _B_setup():
        B, S, Dm, Df = (2, 1, 512, 1792)
        return {'x': _w((lambda *s: torch.randn(*s, dtype=torch.bfloat16) * 0.05)(B, S, Dm)), 'w_gate': _w((lambda *s: torch.randn(*s, dtype=torch.bfloat16) * 3.2)(Dm, Df) * Dm ** (-0.5)), 'w_up': _w((lambda *s: torch.randn(*s, dtype=torch.bfloat16) * 3.2)(Dm, Df) * Dm ** (-0.5)), 'w_down': _w((lambda *s: torch.randn(*s, dtype=torch.bfloat16) * 3.2)(Df, Dm) * Df ** (-0.5))}
    _B_in = _B_setup()
    return {'A_x': _A_in['x'], 'A_c_kv': _A_in['c_kv'], 'A_w_q': _A_in['w_q'], 'A_w_uk': _A_in['w_uk'], 'A_w_uv': _A_in['w_uv'], 'A_w_o': _A_in['w_o'], 'B_x': _B_in['x'], 'B_w_gate': _B_in['w_gate'], 'B_w_up': _B_in['w_up'], 'B_w_down': _B_in['w_down'], 'c': _w((lambda *s: torch.randn(*s, dtype=torch.bfloat16) * 0.1)(2, 512) * 8.0), 'w_mod': _w((lambda *s: torch.randn(*s, dtype=torch.bfloat16) * 0.1)(512, 6 * 512) * 512 ** (-0.5) * 8.0)}

def reference(A_x, A_c_kv, A_w_q, A_w_uk, A_w_uv, A_w_o, B_x, B_w_gate, B_w_up, B_w_down, c, w_mod):

    def _A_ref(x, c_kv, w_q, w_uk, w_uv, w_o):
        B, Sq, M = (x.shape[0], x.shape[1], x.shape[2])
        Sk = c_kv.shape[1]
        H, D = (w_q.shape[1], w_q.shape[2])
        q = torch.einsum('bqm,mhd->bhqd', x, w_q)
        k = torch.einsum('bkc,chd->bhkd', c_kv, w_uk)
        v = torch.einsum('bkc,chd->bhkd', c_kv, w_uv)
        scores = torch.einsum('bhqd,bhkd->bhqk', q, k) * D ** (-0.5)
        off = Sk - Sq
        qi = torch.arange(Sq)[:, None]
        kj = torch.arange(Sk)[None, :]
        cmask = kj <= qi + off
        scores = torch.where(cmask[None, None], scores, -1000000000.0)
        p = _softmax(scores, axis=-1)
        ctx = torch.einsum('bhqk,bhkd->bhqd', p, v)
        return torch.einsum('bhqd,hdm->bqm', ctx, w_o)

    def _B_ref(x, w_gate, w_up, w_down):
        g = torch.einsum('bsd,df->bsf', x, w_gate)
        u = torch.einsum('bsd,df->bsf', x, w_up)
        h = _gelu(g) * u
        return torch.einsum('bsf,fd->bsd', h, w_down)
    x = A_x
    mod = (_silu(c) @ w_mod).reshape(c.shape[0], 6, 1, -1)
    sa, ca, ga, sb, cb, gb = (mod[:, 0].clone(), mod[:, 1].clone(), mod[:, 2].clone(), mod[:, 3].clone(), mod[:, 4].clone(), mod[:, 5].clone())
    h = _layernorm(x, axis=-1) * (1 + ca) + sa
    x = x + ga * _A_ref(h, A_c_kv, A_w_q, A_w_uk, A_w_uv, A_w_o)
    h = _layernorm(x, axis=-1) * (1 + cb) + sb
    x = x + gb * _B_ref(h, B_w_gate, B_w_up, B_w_down)
    return x
```

```cpp
#include <cuda_runtime.h>
#include <cuda_bf16.h>
#include <cuda.h>
#include <stdint.h>

#define WIN 8
#define PACE 640
#define K0 2
#define DLY1 5000
#define D2 0
#define D3 1000
#define D4 900
#define D5 0
#define D6 0
#define D7 250
#define DA 500
#define DF 850
#define DF2 4000
#define STG 0
#define NA 0
#define NB 17
#define NC 29
#define PA 300
#define PB 560
#define PC 760
#define G35 0
#define PD 350
#define DS 400
#define DM 1500
#define MRLATE 1
#define D4B 1
#define PRW 2
#define PRK 2
#define OTMA 0
#define MLS 4
#define T4 0
#define WD 2
#define APE 1
#define PU6 1
#define PUF 1
#define ZW 0
#define NCTA 128
#define NFF 112
#define SPIN_LIMIT (1 << 22)

#define OFF_MOD1 0
#define OFF_QP 65536
#define OFF_QB (OFF_QP + 131072)
#define OFF_BIG (OFF_QB + 65536)
#define OFF_OB OFF_BIG
#define OFF_ML (OFF_OB + 2097152)
#define OFF_CP (OFF_ML + 2048 * MLS)
#define OFF_AP (OFF_CP + 131072)
#define OFF_MR (OFF_AP + 65536)
#define OFF_GP (OFF_MR + 65536)
#define OFF_FP (OFF_GP + NFF * 4096)
#define SCR_USED (OFF_FP + 128 * NFF * 32)
#define ZSHARE 26112
#define SCR_BYTES (OFF_BIG + 128 * ZSHARE)
static_assert(SCR_USED <= SCR_BYTES, "scratch");
__device__ __align__(1024) unsigned char g_scr[SCR_BYTES];
__device__ __align__(128) unsigned int g_sync[32];

#define SM_C 0
#define SM_A 131072
#define SM_B 163840
#define SM_M 196608
#define SM_X 204800
#define SM_MISC 221184
#define SM_BAR (SM_MISC)
#define SM_SC (SM_MISC + 512)
#define SM_XS (SM_SC + 2176)
#define SM_ACT (SM_XS + 2048)
#define SM_ST (SM_ACT + 2560)
#define SM_MX (SM_ST + 256)
#define SM_LS (SM_MX + 1536)
#define SM_ACTB (SM_LS + 1536)
#define SM_END (SM_ACTB + 640)
#define SM_RED SM_X
#define SM_ACT2 (SM_X + 8192)
#define SM_GU (SM_X + 12288)
#define SMEM_BYTES (SM_END)
static_assert(SMEM_BYTES <= 232448, "smem");
#define SM_Q SM_B
#define SM_P (SM_B + 16384)

#define NPIECE 41
#define BAR_FREEA 48
#define BAR_FREEC 49
#define BAR_EX 52
#define BAR_Z1 56
#define BAR_Z2 57
#define ZSRC 1536

struct Params {
    CUtensorMap mod128, wq, wuk, wuv, wo, ckv, gate, up, down;
    const __nv_bfloat16* x;
    const __nv_bfloat16* c;
    const __nv_bfloat16* wmod;
    __nv_bfloat16* out;
};

__device__ __forceinline__ uint32_t smem_u32(const void* p) { return (uint32_t)__cvta_generic_to_shared(p); }
__device__ __forceinline__ void mbar_init(uint32_t bar, int cnt) { asm volatile("mbarrier.init.shared::cta.b64 [%0], %1;" ::"r"(bar), "r"(cnt) : "memory"); }
__device__ __forceinline__ void mbar_expect_tx(uint32_t bar, uint32_t bytes) { asm volatile("mbarrier.arrive.expect_tx.shared::cta.b64 _, [%0], %1;" ::"r"(bar), "r"(bytes) : "memory"); }
__device__ __forceinline__ void mbar_arrive(uint32_t bar) { asm volatile("mbarrier.arrive.shared::cta.b64 _, [%0];" ::"r"(bar) : "memory"); }
__device__ __forceinline__ bool mbar_try(uint32_t bar, uint32_t parity) {
    uint32_t ok;
    asm volatile("{.reg .pred p; mbarrier.try_wait.parity.shared::cta.b64 p,[%1],%2; selp.u32 %0,1,0,p;}" : "=r"(ok) : "r"(bar), "r"(parity) : "memory");
    return ok;
}
__device__ __forceinline__ bool mbar_try_cluster(uint32_t bar, uint32_t parity) {
    uint32_t ok;
    asm volatile("{.reg .pred p; mbarrier.try_wait.parity.acquire.cluster.shared::cta.b64 p,[%1],%2; selp.u32 %0,1,0,p;}" : "=r"(ok) : "r"(bar), "r"(parity) : "memory");
    return ok;
}
__device__ __forceinline__ void mbar_wait(uint32_t bar, uint32_t parity) {
    int it = 0;
    while (!mbar_try(bar, parity)) { if (++it > SPIN_LIMIT) __trap(); }
}
__device__ __forceinline__ void mbar_wait_w(uint32_t bar) { mbar_wait(bar, 0); __syncwarp(); }
__device__ __forceinline__ void tma2d(uint32_t dst, const CUtensorMap* m, int c0, int c1, uint32_t bar, uint64_t pol) {
    asm volatile("cp.async.bulk.tensor.2d.shared::cluster.global.mbarrier::complete_tx::bytes.L2::cache_hint [%0],[%1,{%3,%4}],[%2],%5;" ::"r"(dst), "l"(m), "r"(bar), "r"(c0), "r"(c1), "l"(pol) : "memory");
}
__device__ __forceinline__ void tma3d(uint32_t dst, const CUtensorMap* m, int c0, int c1, int c2, uint32_t bar, uint64_t pol) {
    asm volatile("cp.async.bulk.tensor.3d.shared::cluster.global.mbarrier::complete_tx::bytes.L2::cache_hint [%0],[%1,{%3,%4,%5}],[%2],%6;" ::"r"(dst), "l"(m), "r"(bar), "r"(c0), "r"(c1), "r"(c2), "l"(pol) : "memory");
}
__device__ __forceinline__ void bar_sync(int id, int n) { asm volatile("bar.sync %0, %1;" ::"r"(id), "r"(n) : "memory"); }
#define OLD "ld.relaxed.gpu.global.v4.u32"
__device__ __forceinline__ uint4 ldw4(const void* p) {
    uint4 v;
    asm volatile(OLD " {%0,%1,%2,%3},[%4];" : "=r"(v.x), "=r"(v.y), "=r"(v.z), "=r"(v.w) : "l"(p) : "memory");
    return v;
}
__device__ __forceinline__ uint4 ldv4(const void* p) {
    uint4 v;
    asm volatile("ld.relaxed.gpu.global.v4.u32 {%0,%1,%2,%3},[%4];" : "=r"(v.x), "=r"(v.y), "=r"(v.z), "=r"(v.w) : "l"(p) : "memory");
    return v;
}
__device__ __forceinline__ uint32_t ld1(const void* p) {
    uint32_t v;
    asm volatile("ld.relaxed.gpu.global.u32 %0,[%1];" : "=r"(v) : "l"(p) : "memory");
    return v;
}
__device__ __forceinline__ void stv4(void* p, uint32_t a, uint32_t b, uint32_t c, uint32_t d) {
    asm volatile("st.relaxed.gpu.global.v4.u32 [%0],{%1,%2,%3,%4};" ::"l"(p), "r"(a), "r"(b), "r"(c), "r"(d) : "memory");
}
__device__ __forceinline__ void stv2(void* p, uint32_t a, uint32_t b) {
    asm volatile("st.relaxed.gpu.global.v2.u32 [%0],{%1,%2};" ::"l"(p), "r"(a), "r"(b) : "memory");
}
__device__ __forceinline__ void st1(void* p, uint32_t a) { asm volatile("st.relaxed.gpu.global.u32 [%0],%1;" ::"l"(p), "r"(a) : "memory"); }
__device__ __forceinline__ uint32_t canon(uint32_t w) { return w == 0u ? 0x80000000u : w; }
__device__ __forceinline__ uint32_t canonf(float f) { return canon(__float_as_uint(f)); }
__device__ __forceinline__ bool ok4(const uint4& v) { return v.x != 0u && v.y != 0u && v.z != 0u && v.w != 0u; }
template <int N>
__device__ __forceinline__ void pollN(uint4 (&v)[N], const unsigned char* base, int stride) {
#pragma unroll
    for (int i = 0; i < N; i++) v[i] = ldv4(base + i * stride);
    int it = 0;
    while (true) {
        bool all = true;
#pragma unroll
        for (int i = 0; i < N; i++) all = all && ok4(v[i]);
        if (all) break;
        if (++it > SPIN_LIMIT) __trap();
#pragma unroll
        for (int i = 0; i < N; i++)
            if (!ok4(v[i])) v[i] = ldv4(base + i * stride);
    }
}
template <int C>
__device__ __forceinline__ void delay() {
    if (C > 0) {
        const uint32_t t = clock();
        while ((int)(clock() - t) < C) {}
    }
}
template <int N>
__device__ __forceinline__ void pollS(uint4 (&a)[N], const unsigned char* base, int stride) {
    int it = 0;
    while (true) {
        bool ok = true;
#pragma unroll
        for (int i = 0; i < N; i++) ok = ok && ok4(a[i]);
        if (__all_sync(0xffffffffu, ok)) break;
#pragma unroll
        for (int i = 0; i < N; i++) a[i] = ldv4(base + i * stride);
        if (++it > SPIN_LIMIT) __trap();
    }
}
__device__ __forceinline__ void ldsm4(uint32_t (&r)[4], uint32_t a) {
    asm volatile("ldmatrix.sync.aligned.m8n8.x4.shared.b16 {%0,%1,%2,%3},[%4];" : "=r"(r[0]), "=r"(r[1]), "=r"(r[2]), "=r"(r[3]) : "r"(a) : "memory");
}
__device__ __forceinline__ void ldsm4t(uint32_t (&r)[4], uint32_t a) {
    asm volatile("ldmatrix.sync.aligned.m8n8.x4.trans.shared.b16 {%0,%1,%2,%3},[%4];" : "=r"(r[0]), "=r"(r[1]), "=r"(r[2]), "=r"(r[3]) : "r"(a) : "memory");
}
__device__ __forceinline__ void mma16816(float (&d)[4], const uint32_t (&a)[4], uint32_t b0, uint32_t b1) {
    asm volatile("mma.sync.aligned.m16n8k16.row.col.f32.bf16.bf16.f32 {%0,%1,%2,%3},{%4,%5,%6,%7},{%8,%9},{%0,%1,%2,%3};"
                 : "+f"(d[0]), "+f"(d[1]), "+f"(d[2]), "+f"(d[3]) : "r"(a[0]), "r"(a[1]), "r"(a[2]), "r"(a[3]), "r"(b0), "r"(b1));
}
__device__ __forceinline__ uint32_t pack2(float lo, float hi) {
    uint32_t r;
    asm("cvt.rn.bf16x2.f32 %0,%1,%2;" : "=r"(r) : "f"(hi), "f"(lo));
    return r;
}
__device__ __forceinline__ float bflo(uint32_t w) { return __uint_as_float(w << 16); }
__device__ __forceinline__ float bfhi(uint32_t w) { return __uint_as_float(w & 0xffff0000u); }
__device__ __forceinline__ uint4 lds128(uint32_t a) {
    uint4 v;
    asm volatile("ld.shared.v4.u32 {%0,%1,%2,%3},[%4];" : "=r"(v.x), "=r"(v.y), "=r"(v.z), "=r"(v.w) : "r"(a) : "memory");
    return v;
}
__device__ __forceinline__ uint2 lds64(uint32_t a) {
    uint2 v;
    asm volatile("ld.shared.v2.u32 {%0,%1},[%2];" : "=r"(v.x), "=r"(v.y) : "r"(a) : "memory");
    return v;
}
__device__ __forceinline__ uint32_t lds32(uint32_t a) {
    uint32_t v;
    asm volatile("ld.shared.u32 %0,[%1];" : "=r"(v) : "r"(a) : "memory");
    return v;
}
__device__ __forceinline__ void sts128(uint32_t a, uint4 v) { asm volatile("st.shared.v4.u32 [%0],{%1,%2,%3,%4};" ::"r"(a), "r"(v.x), "r"(v.y), "r"(v.z), "r"(v.w) : "memory"); }
__device__ __forceinline__ void sts64(uint32_t a, uint32_t x, uint32_t y) { asm volatile("st.shared.v2.u32 [%0],{%1,%2};" ::"r"(a), "r"(x), "r"(y) : "memory"); }
__device__ __forceinline__ void sts32(uint32_t a, uint32_t x) { asm volatile("st.shared.u32 [%0],%1;" ::"r"(a), "r"(x) : "memory"); }
__device__ __forceinline__ void sts16(uint32_t a, float f) {
    unsigned short h = __bfloat16_as_ushort(__float2bfloat16_rn(f));
    asm volatile("st.shared.u16 [%0],%1;" ::"r"(a), "h"(h) : "memory");
}
__device__ __forceinline__ float ex2(float x) { float y; asm("ex2.approx.ftz.f32 %0,%1;" : "=f"(y) : "f"(x)); return y; }
__device__ __forceinline__ float shx(float v, int m) { return __shfl_xor_sync(0xffffffffu, v, m); }
#define SM_BASE 1024
__device__ __forceinline__ uint32_t mkdesc(uint32_t off) { return ((SM_BASE + off) >> 4) | (1u << 16); }
template <int TA>
__device__ __forceinline__ void wgmma_n32(float (&d)[16], uint32_t da, uint32_t db, uint32_t sd) {
    asm volatile(
        "{.reg .pred p; .reg .b64 a, b; setp.ne.b32 p, %18, 0; mov.b64 a, {%16, 0x40000040}; mov.b64 b, {%17, 0x40000040};\n"
        "wgmma.mma_async.sync.aligned.m64n32k16.f32.bf16.bf16 {%0,%1,%2,%3,%4,%5,%6,%7,%8,%9,%10,%11,%12,%13,%14,%15}, a, b, p, 1, 1, %19, 0;}\n"
        : "+f"(d[0]), "+f"(d[1]), "+f"(d[2]), "+f"(d[3]), "+f"(d[4]), "+f"(d[5]), "+f"(d[6]), "+f"(d[7]), "+f"(d[8]), "+f"(d[9]), "+f"(d[10]),
          "+f"(d[11]), "+f"(d[12]), "+f"(d[13]), "+f"(d[14]), "+f"(d[15])
        : "r"(da), "r"(db), "r"(sd), "n"(TA)
        : "memory");
}
__device__ __forceinline__ void wg_fence() { asm volatile("wgmma.fence.sync.aligned;" ::: "memory"); }
__device__ __forceinline__ void wg_commit() { asm volatile("wgmma.commit_group.sync.aligned;" ::: "memory"); }
__device__ __forceinline__ void wg_wait0() { asm volatile("wgmma.wait_group.sync.aligned 0;" ::: "memory"); }
__device__ __forceinline__ void fence_async() { asm volatile("fence.proxy.async.shared::cta;" ::: "memory"); }
#define TS(i)
#define TK(i)

template <bool ALLCOLS>
__device__ __forceinline__ void load_b128(uint32_t (&bf)[16], uint32_t act, int lane) {
    if (ALLCOLS || lane < 8) {
#pragma unroll
        for (int i = 0; i < 4; i++) {
            uint4 v = lds128(act + lane * 80 + i * 16);
            bf[4 * i] = v.x; bf[4 * i + 1] = v.y; bf[4 * i + 2] = v.z; bf[4 * i + 3] = v.w;
        }
    } else {
#pragma unroll
        for (int i = 0; i < 16; i++) bf[i] = 0u;
    }
}
__device__ __forceinline__ void load_a_t(uint32_t (&af)[8][4], uint32_t base, int warp, int lane) {
    const int chunk = 2 * (warp & 3) + ((lane >> 3) & 1);
    const uint32_t a0 = base + (warp >> 2) * 16384 + ((lane & 7) + 8 * (lane >> 4)) * 128 + ((chunk ^ (lane & 7)) << 4);
#pragma unroll
    for (int ks = 0; ks < 8; ks++) ldsm4t(af[ks], a0 + ks * 2048);
}
__device__ __forceinline__ void mma_k128(float (&d)[4], const uint32_t (&af)[8][4], const uint32_t (&bf)[16]) {
    float e[4] = {0.f, 0.f, 0.f, 0.f};
    d[0] = d[1] = d[2] = d[3] = 0.f;
#pragma unroll
    for (int ks = 0; ks < 8; ks += 2) {
        mma16816(d, af[ks], bf[2 * ks], bf[2 * ks + 1]);
        mma16816(e, af[ks + 1], bf[2 * ks + 2], bf[2 * ks + 3]);
    }
    d[0] += e[0]; d[1] += e[1]; d[2] += e[2]; d[3] += e[3];
}
template <int N>
__device__ __forceinline__ void pollU(uint4 (&a)[N], const unsigned char* base, int stride) {
    for (int it = 0;; it++) {
        bool done = true;
#pragma unroll
        for (int i = 0; i < N; i++) {
            if (!__all_sync(0xffffffffu, ok4(a[i]))) { a[i] = ldv4(base + i * stride); done = false; }
        }
        if (done) break;
        if (it > SPIN_LIMIT) __trap();
    }
}
template <class Fn>
__device__ __forceinline__ void gather4(const unsigned char* blk, uint32_t act, int tid, int warp, int lane, Fn mid) {
    uint4 v[1];
    v[0] = ldv4(blk + tid * 16);
    mid();
    pollS<1>(v, blk + tid * 16, 0);
    float a = __uint_as_float(v[0].x), b = __uint_as_float(v[0].y), c = __uint_as_float(v[0].z), d = __uint_as_float(v[0].w);
    const bool up = lane & 16;
    float s0 = up ? a : c, s1 = up ? b : d, k0 = up ? c : a, k1 = up ? d : b;
    k0 += shx(s0, 16); k1 += shx(s1, 16);
    const bool u8 = lane & 8;
    float s = u8 ? k0 : k1, k = u8 ? k1 : k0;
    k += shx(s, 8);
    const int hi = lane >> 4, bb = (lane >> 3) & 1, g = lane & 7;
    sts16(act + (bb * 4 + (g >> 1)) * 80 + warp * 8 + ((g & 1) + 2 * hi) * 2, k);
}

__device__ __forceinline__ void bulk_st(void* dst, uint32_t src, uint32_t bytes) {
    asm volatile("cp.async.bulk.global.shared::cta.bulk_group [%0],[%1],%2;" ::"l"(dst), "r"(src), "r"(bytes) : "memory");
}
__device__ __forceinline__ float sum4(const uint4& v) {
    return (__uint_as_float(v.x) + __uint_as_float(v.y)) + (__uint_as_float(v.z) + __uint_as_float(v.w));
}

__global__ void __cluster_dims__(2, 1, 1) __launch_bounds__(320, 1) fused_kernel(const __grid_constant__ Params p) {
    extern __shared__ __align__(1024) unsigned char smem_raw[];
    const uint32_t sb = smem_u32(smem_raw);
    const int tid = threadIdx.x, warp = tid >> 5, lane = tid & 31;
    const int cta = blockIdx.x;
    const uint32_t bars = sb + SM_BAR;
    unsigned char* const scr = g_scr;
    const uint32_t tstart = clock();
    TS(warp < 8 ? 0 : (warp == 8 ? 20 : 24));

    if (warp < 8) {
        const int r = tid >> 2, c4 = tid & 3;
        const __nv_bfloat16* src = p.wmod + (size_t)(128 * (cta & 3) + r) * 3072 + 32 * (cta >> 2) + c4 * 8;
        const uint32_t dst = sb + SM_M + r * 64 + ((c4 ^ ((r >> 1) & 3)) << 4);
        asm volatile("cp.async.cg.shared.global [%0],[%1],16;" ::"r"(dst), "l"(src) : "memory");
        asm volatile("cp.async.cg.shared.global [%0],[%1],16;" ::"r"(dst + 4096), "l"(src + 64 * 3072) : "memory");
    }
    uint64_t pol;
    asm volatile("createpolicy.fractional.L2::evict_first.b64 %0, 1.0;" : "=l"(pol));
    if (tid == 256) {
#pragma unroll
        for (int i = 1; i <= 4; i++) mbar_init(bars + 8 * i, 1);
        fence_async();
#pragma unroll
        for (int j = 0; j < K0; j++) {
            mbar_expect_tx(bars + 8 * (1 + j), 8192);
            tma2d(sb + SM_A + (j & 1) * 16384 + (j >> 1) * 8192, &p.wq, (cta >> 2) * 128 + (j & 1) * 64, (cta & 3) * 128 + (j >> 1) * 64, bars + 8 * (1 + j), pol);
        }
        TS(30);
#pragma unroll
        for (int i = 5; i < NPIECE; i++) mbar_init(bars + 8 * i, 1);
#pragma unroll
        for (int i = 0; i < 3; i++) mbar_init(bars + 8 * (BAR_FREEA + i), 8);
#pragma unroll
        for (int i = 0; i < 6; i++) mbar_init(bars + 8 * (BAR_EX + i), 1);
        asm volatile("fence.mbarrier_init.release.cluster;" ::: "memory");
        fence_async();
        TS(32);
    }
    if (warp == 8) {
        __syncwarp();
        asm volatile("barrier.cluster.arrive.relaxed.aligned;" ::: "memory");
        asm volatile("bar.arrive 3, 320;" ::: "memory");
        const int h = cta >> 2, sl = cta & 3;
        const int np = cta < NFF ? NPIECE : 35;
        uint32_t ta[2], tb[2];
#pragma unroll
        for (int u = 0; u < 2; u++) {
            const int n = lane + 32 * u;
            int c0, c1, mi, xb = 0;
            uint32_t dst;
            if (n >= 9 && n < 25) {
                const int j = n - 9;
                mi = 5; c0 = (cta & 1) * 256 + (j & 3) * 64; c1 = (cta >> 1) * 256 + (j >> 2) * 64; dst = SM_C + j * 8192;
            } else if (n == 29 || n == 30) {
                mi = 0; c0 = 1024 + 64 * h; c1 = sl * 128 + (n - 29) * 64; dst = SM_C + (n - 29) * 8192;
            } else {
                const int j = (n < 29 ? n - 1 : n - 3) & 3;
                const int j0 = (j & 1) * 64, j1 = (j >> 1) * 64;
                c0 = h * 128 + j0; c1 = sl * 128 + j1;
                if (n < 5) { mi = 1; dst = SM_A; }
                else if (n < 9) { mi = 2; dst = SM_B; }
                else if (n < 29) { mi = 3; dst = SM_A; }
                else if (n < 35) { mi = 4; dst = SM_C + 32768; c0 = sl * 128 + j0; c1 = h * 128 + j1; }
                else { mi = 6 + (j & 1); dst = SM_C + 65536; c0 = 64 * h; }
                dst += (j & 1) * 16384 + (j >> 1) * 8192;
            }
            if (n == 25) xb = BAR_FREEA;
            if (n == 29) xb = BAR_FREEC;
            if (n == 35) xb = BAR_FREEC + 1;
            ta[u] = (uint32_t)c0 | ((uint32_t)c1 << 16);
            const uint32_t gap = n < NA ? PA : (n < NB ? PACE : (n < NC ? PB : (n < 35 ? PC : PD)));
            tb[u] = (dst >> 13) | ((uint32_t)mi << 5) | ((uint32_t)xb << 9) | (gap << 16);
        }
        uint32_t tnext = clock();
        const int n2d = np < 39 ? np : 39;
#pragma unroll 1
        for (int n = K0 + 1; n < n2d; n++) {
            const uint32_t pa = __shfl_sync(0xffffffffu, n < 32 ? ta[0] : ta[1], n & 31);
            const uint32_t pb = __shfl_sync(0xffffffffu, n < 32 ? tb[0] : tb[1], n & 31);
            if (n > WIN) mbar_wait(bars + 8 * (n - WIN), 0);
            if (pb & 0xfe00u) mbar_wait(bars + ((pb >> 6) & 0x3f8u), 0);
            while ((int)(clock() - tnext) < 0) {}
            tnext = clock() + (pb >> 16);
            if (lane == 0) {
                const uint32_t bar = bars + 8 * n;
                mbar_expect_tx(bar, 8192);
                tma2d(sb + ((pb & 31u) << 13), &p.mod128 + ((pb >> 5) & 15u), pa & 0xffffu, pa >> 16, bar, pol);
            }
            __syncwarp();
        }
        if (np > 39) {
#pragma unroll
            for (int n = 39; n < 41; n++) {
                mbar_wait(bars + 8 * (n - WD), 0);
                if (lane == 0) {
                    mbar_expect_tx(bars + 8 * n, 8192);
                    tma3d(sb + SM_C + 16384 + (n - 39) * 8192, &p.down, 0, 16 * cta, 4 * (n - 39), bars + 8 * n, pol);
                }
                __syncwarp();
            }
        }
        for (int n = np - WIN; n < np; n++) mbar_wait(bars + 8 * n, 0);
        TS(23);
        __syncwarp();
        asm volatile("barrier.cluster.wait.aligned;" ::: "memory");
        return;
    }
    const uint32_t epoch = ld1(&g_sync[0]);
    if (warp < 8) {
        const int b = tid >> 7, i = tid & 127;
        uint2 cv = *reinterpret_cast<const uint2*>(p.c + b * 512 + 4 * i);
        uint2 xv = *reinterpret_cast<const uint2*>(p.x + b * 512 + 4 * i);
        float c0 = bflo(cv.x), c1 = bfhi(cv.x), c2 = bflo(cv.y), c3 = bfhi(cv.y);
        c0 = c0 / (1.f + __expf(-c0)); c1 = c1 / (1.f + __expf(-c1));
        c2 = c2 / (1.f + __expf(-c2)); c3 = c3 / (1.f + __expf(-c3));
        const int ks = i >> 2, kk = (4 * i) & 15;
        const int q0 = (kk & 7) >> 1, hi = kk >> 3;
        sts32(sb + SM_SC + (b * 4 + q0) * 272 + ks * 8 + hi * 4, pack2(c0, c1));
        sts32(sb + SM_SC + (b * 4 + q0 + 1) * 272 + ks * 8 + hi * 4, pack2(c2, c3));
        sts64(sb + SM_XS + b * 1024 + i * 8, xv.x, xv.y);
        float x0 = bflo(xv.x), x1 = bfhi(xv.x), x2 = bflo(xv.y), x3 = bfhi(xv.y);
        float ls1 = (x0 + x1) + (x2 + x3);
        float ls2 = x0 * x0 + x1 * x1 + x2 * x2 + x3 * x3;
#pragma unroll
        for (int m = 16; m >= 1; m >>= 1) { ls1 += shx(ls1, m); ls2 += shx(ls2, m); }
        if (lane == 0) sts64(sb + SM_ST + warp * 8, __float_as_uint(ls1), __float_as_uint(ls2));
    } else {
#pragma unroll
        for (int i = 0; i < ZSRC / 512; i++) sts128(sb + SM_LS + i * 512 + lane * 16, make_uint4(0u, 0u, 0u, 0u));
        fence_async();
        __syncwarp();
        if (lane == 0) {
            bulk_st(scr + OFF_QP + cta * 1536, sb + SM_LS, 1536);
            asm volatile("cp.async.bulk.commit_group;" ::: "memory");
        }
    }
    asm volatile("cp.async.wait_all;" ::: "memory");
    TS(warp < 8 ? 33 : 34);
    asm volatile("barrier.cluster.arrive.relaxed.aligned;" ::: "memory");
    bar_sync(3, 320);
    TS(warp < 8 ? 35 : 36);
    const int g = lane >> 2, q = lane & 3;
    const int h = cta >> 2, sl = cta & 3;
    uint32_t af[8][4];
    uint32_t bf[16];
    float d[4];

    if (warp == 9) {
        if (lane == 0) {
            asm volatile("cp.async.bulk.wait_group 0;" ::: "memory");
            TS(28);
            asm volatile("red.relaxed.gpu.global.add.u32 [%0],1;" ::"l"(&g_sync[1]) : "memory");
            const uint32_t target = (epoch + 1u) * NCTA;
            int it = 0;
            while ((int)(ld1(&g_sync[1]) - target) < 0) { if (++it > SPIN_LIMIT) __trap(); }
            mbar_arrive(bars + 8 * BAR_Z1);
            TS(29);
        }
        __syncwarp();
        bar_sync(7, 64);
        if (lane == 0) {
#pragma unroll 1
            for (int i = 0; i < ZSHARE / ZSRC; i++) bulk_st(scr + OFF_BIG + cta * ZSHARE + i * ZSRC, sb + SM_LS, ZSRC);
            bulk_st(scr + OFF_MOD1 + ((epoch & 1u) ^ 1u) * 32768 + cta * 256, sb + SM_LS, 256);
            asm volatile("cp.async.bulk.commit_group;" ::: "memory");
            const uint32_t target = (epoch + 1u) * NCTA;
            int it = 0;
            asm volatile("cp.async.bulk.wait_group 0;" ::: "memory");
            asm volatile("red.relaxed.gpu.global.add.u32 [%0],1;" ::"l"(&g_sync[2]) : "memory");
            while ((int)(ld1(&g_sync[2]) - target) < 0) { if (++it > SPIN_LIMIT) __trap(); }
            mbar_arrive(bars + 8 * BAR_Z2);
            TS(36);
        }
        __syncwarp();
        asm volatile("barrier.cluster.wait.aligned;" ::: "memory");
        if (lane < 8) {
#pragma unroll
            for (int i = 0; i < 4; i++) {
                uint4 v = lds128(sb + SM_SC + lane * 272 + sl * 64 + i * 16);
                bf[4 * i] = v.x; bf[4 * i + 1] = v.y; bf[4 * i + 2] = v.z; bf[4 * i + 3] = v.w;
            }
        } else {
#pragma unroll
            for (int i = 0; i < 16; i++) bf[i] = 0u;
        }
        mbar_wait_w(bars + 8 * 29);
        mbar_wait_w(bars + 8 * 30);
#pragma unroll 1
        for (int mt = 0; mt < 4; mt++) {
            load_a_t(af, sb + SM_C, mt, lane);
            mma_k128(d, af, bf);
            if (q == 0) {
                unsigned char* o = scr + OFF_MR + (h >> 3) * 16384 + ((h & 7) >> 1) * 4096 + (32 * (4 * (h & 1) + mt) + 4 * g) * 16 + sl * 4;
#pragma unroll
                for (int i = 0; i < 4; i++) st1(o + i * 16, canonf(d[i]));
            }
        }
        TS(25);
        float ga = 0.f, gb = 0.f;
        delay<DM>();
        if (lane < 16) {
            uint4 v[1];
            pollN<1>(v, scr + OFF_MR + (lane >> 3) * 3 * 16384 + (h >> 3) * 4096 + (32 * (h & 7) + 8 * sl + (lane & 7)) * 16, 0);
            ga = sum4(v[0]);
        }
        __syncwarp();
        const int vi = lane >> 2;
        gb = __shfl_sync(0xffffffffu, ga, 8 + vi);
        ga = __shfl_sync(0xffffffffu, ga, vi);
        const int e = lane >> 4, hi = (lane >> 3) & 1, bb = (lane >> 2) & 1;
        const float xv = __bfloat162float(p.x[bb * 512 + 16 * h + 2 * sl + e + 8 * hi]);
        float x1;
        {
            uint4 v[1];
            bar_sync(5, 64);
            if (cta < NFF) {
                uint32_t xp[4];
#pragma unroll
                for (int i = 0; i < 4; i++) xp[i] = lds32(sb + SM_XS + (lane >> 4) * 1024 + (sl * 128 + 64 * (i >> 1) + 16 * ((lane >> 2) & 3) + 2 * q + 8 * (i & 1)) * 2);
                bar_sync(10, 288);
                float s1 = 0.f, s2 = 0.f;
#pragma unroll
                for (int c = 0; c < 2; c++) {
                    const uint32_t ra = sb + SM_RED + 4096 + (c * 32 + lane) * 16;
                    const uint4 r0 = lds128(ra), r1 = lds128(ra + 1024), r2 = lds128(ra + 2048), r3 = lds128(ra + 3072);
                    const uint32_t gaa = sb + SM_GU + 2048 + (32 * (4 * c + ((lane >> 2) & 3)) + 8 * q + (lane >> 4)) * 4;
                    const float y0 = bflo(xp[2 * c]) + __uint_as_float(lds32(gaa)) * ((__uint_as_float(r0.x) + __uint_as_float(r1.x)) + (__uint_as_float(r2.x) + __uint_as_float(r3.x)));
                    const float y1 = bflo(xp[2 * c + 1]) + __uint_as_float(lds32(gaa + 8)) * ((__uint_as_float(r0.y) + __uint_as_float(r1.y)) + (__uint_as_float(r2.y) + __uint_as_float(r3.y)));
                    const float y2 = bfhi(xp[2 * c]) + __uint_as_float(lds32(gaa + 16)) * ((__uint_as_float(r0.z) + __uint_as_float(r1.z)) + (__uint_as_float(r2.z) + __uint_as_float(r3.z)));
                    const float y3 = bfhi(xp[2 * c + 1]) + __uint_as_float(lds32(gaa + 24)) * ((__uint_as_float(r0.w) + __uint_as_float(r1.w)) + (__uint_as_float(r2.w) + __uint_as_float(r3.w)));
                    s1 += (y0 + y1) + (y2 + y3);
                    s2 += (y0 * y0 + y1 * y1) + (y2 * y2 + y3 * y3);
                }
                float k = ((lane & 1) ? s2 : s1) + shx((lane & 1) ? s1 : s2, 1);
#pragma unroll
                for (int m = 2; m <= 8; m <<= 1) k += shx(k, m);
                if ((lane & 8) == 0) st1(scr + OFF_GP + (4 * h + ((lane >> 1) & 3)) * 4096 + 3072 + ((lane & 1) * 2 + (lane >> 4)) * 16 + sl * 4, canonf(k));
                TS(34);
            } else delay<DA>();
            pollN<1>(v, scr + OFF_AP + ((h >> 3) * 32 + lane) * 512 + (h & 7) * 64 + sl * 16, 0);
            __syncwarp();
            const float a[8] = {bflo(v[0].x), bfhi(v[0].x), bflo(v[0].y), bfhi(v[0].y), bflo(v[0].z), bfhi(v[0].z), bflo(v[0].w), bfhi(v[0].w)};
            float k4[4], k2[2];
#pragma unroll
            for (int i = 0; i < 4; i++) k4[i] = (e ? a[4 + i] : a[i]) + shx(e ? a[i] : a[4 + i], 16);
#pragma unroll
            for (int i = 0; i < 2; i++) k2[i] = (hi ? k4[2 + i] : k4[i]) + shx(hi ? k4[i] : k4[2 + i], 8);
            float k = (bb ? k2[1] : k2[0]) + shx(bb ? k2[0] : k2[1], 4);
            k += shx(k, 2);
            k += shx(k, 1);
            x1 = xv + ga * k;
        }
        TS(26);
        {
            uint4 v[7];
            if (cta < NFF) { bar_sync(6, 64); delay<DF>(); } else delay<DF2>();
#pragma unroll
            for (int i = 0; i < 7; i++) v[i] = ldv4(scr + OFF_FP + cta * (NFF * 32) + lane * 16 + i * 512);
            pollU<7>(v, scr + OFF_FP + cta * (NFF * 32) + lane * 16, 512);
            float s[4] = {0.f, 0.f, 0.f, 0.f};
#pragma unroll
            for (int i = 0; i < 7; i++) {
                s[0] += __uint_as_float(v[i].x); s[1] += __uint_as_float(v[i].y);
                s[2] += __uint_as_float(v[i].z); s[3] += __uint_as_float(v[i].w);
            }
            const int h2 = lane >> 4, b2 = (lane >> 3) & 1, e2 = lane & 1;
            float k2[2];
#pragma unroll
            for (int i = 0; i < 2; i++) k2[i] = (h2 ? s[2 + i] : s[i]) + shx(h2 ? s[i] : s[2 + i], 16);
            float k = (b2 ? k2[1] : k2[0]) + shx(b2 ? k2[0] : k2[1], 8);
            k += shx(k, 4);
            k += shx(k, 2);
            const int src = (e2 * 4 + h2 * 2 + b2) * 4;
            const float xx = __shfl_sync(0xffffffffu, x1, src), gg = __shfl_sync(0xffffffffu, gb, src);
            if ((lane & 6) == 0) p.out[b2 * 512 + 16 * h + 2 * sl + e2 + 8 * h2] = __float2bfloat16_rn(xx + gg * k);
            if (cta == 0 && lane == 0) st1(&g_sync[0], epoch + 1u);
        }
        TS(27);
        return;
    }
    const uint32_t act = sb + SM_ACT;
    unsigned char* const mod1 = scr + OFF_MOD1 + (epoch & 1u) * 32768;
    if (warp < 2) {
        const int kr = (lane & 7) + 8 * (lane >> 4);
        const int ch = 2 * warp + ((lane >> 3) & 1);
        const uint32_t a0 = sb + SM_M + kr * 64 + ((ch ^ ((kr >> 1) & 3)) << 4);
#pragma unroll
        for (int ks = 0; ks < 8; ks++) ldsm4t(af[ks], a0 + ks * 1024);
        if (lane < 8) {
#pragma unroll
            for (int i = 0; i < 4; i++) {
                uint4 v = lds128(sb + SM_SC + lane * 272 + (cta & 3) * 64 + i * 16);
                bf[4 * i] = v.x; bf[4 * i + 1] = v.y; bf[4 * i + 2] = v.z; bf[4 * i + 3] = v.w;
            }
        } else {
#pragma unroll
            for (int i = 0; i < 16; i++) bf[i] = 0u;
        }
        mma_k128(d, af, bf);
        if (q == 0) stv4(mod1 + (((cta >> 2) * 2 + warp) * 4 + (cta & 3)) * 128 + g * 16, canonf(d[0]), canonf(d[1]), canonf(d[2]), canonf(d[3]));
    }
    TS(1);
    {
        const int hi = lane >> 4, bb = (lane >> 3) & 1, g8 = lane & 7;
        float s1 = 0.f, s2 = 0.f;
#pragma unroll
        for (int i = 0; i < 4; i++) {
            uint2 t = lds64(sb + SM_ST + (bb * 4 + i) * 8);
            s1 += __uint_as_float(t.x); s2 += __uint_as_float(t.y);
        }
        const float mu = s1 * (1.f / 512.f);
        const float rs = rsqrtf(fmaxf(s2 * (1.f / 512.f) - mu * mu, 0.f) + 1e-5f);
        unsigned short xh;
        asm volatile("ld.shared.u16 %0,[%1];" : "=h"(xh) : "r"(sb + SM_XS + bb * 1024 + (sl * 128 + 16 * warp + g8 + 8 * hi) * 2) : "memory");
        const float xn = (__uint_as_float((uint32_t)xh << 16) - mu) * rs;
#pragma unroll
        for (int i = 1; i < 5; i++) mbar_wait_w(bars + 8 * i);
        load_a_t(af, sb + SM_A, warp, lane);
        if ((sb & 0x3ffffu) != SM_BASE) __trap();
        asm volatile("barrier.cluster.wait.aligned;" ::: "memory");
        uint4 v[2];
        while ((int)(clock() - tstart) < DLY1) {}
        v[0] = ldv4(mod1 + sl * 4096 + tid * 16);
        v[1] = ldv4(mod1 + sl * 4096 + tid * 16 + 16384);
        pollS<2>(v, mod1 + sl * 4096 + tid * 16, 16384);
        const float x0 = __shfl_sync(0xffffffffu, xn, g8), x1 = __shfl_sync(0xffffffffu, xn, g8 + 8);
        const float x2 = __shfl_sync(0xffffffffu, xn, g8 + 16), x3 = __shfl_sync(0xffffffffu, xn, g8 + 24);
        const float a0 = fmaf(x0, __uint_as_float(v[1].x), __uint_as_float(v[0].x)), a1 = fmaf(x1, __uint_as_float(v[1].y), __uint_as_float(v[0].y));
        const float a2 = fmaf(x2, __uint_as_float(v[1].z), __uint_as_float(v[0].z)), a3 = fmaf(x3, __uint_as_float(v[1].w), __uint_as_float(v[0].w));
        const float k0 = (hi ? a2 : a0) + shx(hi ? a0 : a2, 16), k1 = (hi ? a3 : a1) + shx(hi ? a1 : a3, 16);
        const float k = (bb ? k1 : k0) + shx(bb ? k0 : k1, 8);
        sts16(act + (bb * 4 + (g8 >> 1)) * 80 + warp * 8 + ((g8 & 1) + 2 * hi) * 2, xn + k);
    }
    TS(2);
    bar_sync(1, 256);
    load_b128<false>(bf, act, lane);
    mma_k128(d, af, bf);
    mbar_wait_w(bars + 8 * BAR_Z1);
    if (q == 0) stv4(scr + OFF_QP + h * 4096 + (warp * 4 + sl) * 128 + g * 16, canonf(d[0]), canonf(d[1]), canonf(d[2]), canonf(d[3]));
    __syncwarp();
    if (lane == 0) mbar_arrive(bars + 8 * BAR_FREEA);
    TS(3);
#pragma unroll
    for (int i = 5; i < 9; i++) mbar_wait_w(bars + 8 * i);
    {
        const int row = 16 * warp + (lane & 7) + 8 * ((lane >> 3) & 1);
#pragma unroll
        for (int ks = 0; ks < 8; ks++) {
            const int kc = 2 * ks + (lane >> 4);
            ldsm4(af[ks], sb + SM_B + (kc >> 3) * 16384 + row * 128 + (((kc & 7) ^ (row & 7)) << 4));
        }
    }
    delay<D2>();
    gather4(scr + OFF_QP + h * 4096, sb + SM_ACTB, tid, warp, lane, []() {});
    TS(4);
    bar_sync(1, 256);
    load_b128<false>(bf, sb + SM_ACTB, lane);
    mma_k128(d, af, bf);
    {
        const float sc = 0.08838834764831845f * 1.4426950408889634f;
        uint32_t w0 = pack2(d[0] * sc, d[1] * sc), w1 = pack2(d[2] * sc, d[3] * sc);
        asm volatile("movmatrix.sync.aligned.m8n8.trans.b16 %0,%0;" : "+r"(w0));
        asm volatile("movmatrix.sync.aligned.m8n8.trans.b16 %0,%0;" : "+r"(w1));
        if (lane < 8) {
            unsigned char* o = scr + OFF_QB + (((lane >> 2) * 2 + (sl >> 1)) * 4 + 2 * (sl & 1) + (warp >> 2)) * 4096 + h * 128 + (lane & 3) * 4;
            st1(o + (((2 * (warp & 3)) ^ (h & 7)) << 4), canon(w0));
            st1(o + (((2 * (warp & 3) + 1) ^ (h & 7)) << 4), canon(w1));
        }
    }
    TS(5);
    const int cl = cta >> 1, rk = cta & 1, bat = cl >> 5;
    {
        uint4 v[4];
        delay<D3>();
        pollN<4>(v, scr + OFF_QB + (bat * 2 + rk) * 16384 + tid * 16, 4096);
#pragma unroll
        for (int i = 0; i < 4; i++) sts128(sb + SM_Q + tid * 16 + i * 4096, v[i]);
        if (warp == ZW) asm volatile("bar.arrive 7, 64;" ::: "memory");
        TS(1);
        fence_async();
    }
    bar_sync(1, 256);
    TS(6);
    const int wg = __shfl_sync(0xffffffffu, warp >> 2, 0), w4 = warp & 3;
    float o0[16], o1[16];
    {
        float lsum[8], s[16];
#pragma unroll
        for (int i = 0; i < 16; i++) { o0[i] = 0.f; o1[i] = 0.f; }
        uint32_t peer;
        asm volatile("mapa.shared::cluster.u32 %0,%1,%2;" : "=r"(peer) : "r"(sb), "r"(rk ^ 1));
        const uint32_t dq = mkdesc(SM_Q);
        auto scores = [&](int k) {
            const uint32_t xo = (k & 2) ? (wg ? SM_B + 24576 : SM_M) : SM_X + wg * 8192;
            const uint32_t dc = mkdesc(SM_C + k * 32768);
            if ((tid & 127) == 0) mbar_expect_tx(bars + 8 * (BAR_EX + k), 8192);
#pragma unroll
            for (int st = 0; st < 4; st++) {
                mbar_wait_w(bars + 8 * (9 + 4 * k + st));
                if (k < 2 && st == 0) TS(33);
                wg_fence();
#pragma unroll
                for (int kk = 0; kk < 4; kk++) wgmma_n32<0>(s, dc + st * 512 + kk * 2, dq + st * 256 + kk * 2, (st | kk) != 0);
                wg_commit();
            }
            wg_wait0();
            if (k < 2) TS(35);
#pragma unroll
            for (int j = 0; j < 4; j++)
                asm volatile("st.async.weak.shared::cluster.mbarrier::complete_tx::bytes.v4.f32 [%0],{%1,%2,%3,%4},[%5];" ::"r"(peer + xo + (tid & 127) * 16 + j * 2048),
                             "f"(s[4 * j]), "f"(s[4 * j + 1]), "f"(s[4 * j + 2]), "f"(s[4 * j + 3]), "r"(peer + SM_BAR + 8 * (BAR_EX + k))
                             : "memory");
        };
        float mo[8], mslot = -INFINITY;
#pragma unroll 1
        for (int r = 0; r < 2; r++) {
            scores(2 * r + wg);
            if (r == 1 && lane == 0) mbar_arrive(bars + 8 * BAR_FREEC);
            TS(37 + 6 * r);
            const uint32_t xo = sb + (r ? (wg ? SM_B + 24576 : SM_M) : SM_X + wg * 8192) + (tid & 127) * 16;
            mbar_wait_w(bars + 8 * (BAR_EX + 2 * r + wg));
            TS(38 + 6 * r);
#pragma unroll
            for (int j = 0; j < 4; j++) {
                uint4 v = lds128(xo + j * 2048);
                s[4 * j] += __uint_as_float(v.x); s[4 * j + 1] += __uint_as_float(v.y);
                s[4 * j + 2] += __uint_as_float(v.z); s[4 * j + 3] += __uint_as_float(v.w);
            }
            float t[8];
#pragma unroll
            for (int j = 0; j < 4; j++) { t[2 * j] = fmaxf(s[4 * j], s[4 * j + 2]); t[2 * j + 1] = fmaxf(s[4 * j + 1], s[4 * j + 3]); }
            {
                const bool u16 = lane & 16, u8 = lane & 8, u4 = lane & 4;
                float k4[4], k2[2];
#pragma unroll
                for (int i = 0; i < 4; i++) k4[i] = fmaxf(u16 ? t[4 + i] : t[i], shx(u16 ? t[i] : t[4 + i], 16));
#pragma unroll
                for (int i = 0; i < 2; i++) k2[i] = fmaxf(u8 ? k4[2 + i] : k4[i], shx(u8 ? k4[i] : k4[2 + i], 8));
                const float k1 = fmaxf(u4 ? k2[1] : k2[0], shx(u4 ? k2[0] : k2[1], 4));
                sts32(sb + SM_MX + (q * 8 + g) * 48 + warp * 4, __float_as_uint(k1));
            }
            bar_sync(1, 256);
            {
                const uint4 a = lds128(sb + SM_MX + lane * 48), b = lds128(sb + SM_MX + lane * 48 + 16);
                mslot = fmaxf(fmaxf(fmaxf(mslot, __uint_as_float(a.x)), fmaxf(__uint_as_float(a.y), __uint_as_float(a.z))),
                              fmaxf(fmaxf(__uint_as_float(a.w), __uint_as_float(b.x)), fmaxf(fmaxf(__uint_as_float(b.y), __uint_as_float(b.z)), __uint_as_float(b.w))));
#pragma unroll
                for (int i = 0; i < 8; i++) t[i] = __shfl_sync(0xffffffffu, mslot, q * 8 + i);
            }
            uint32_t pk[8];
#pragma unroll
            for (int j = 0; j < 4; j++) {
                const float p0 = ex2(s[4 * j] - t[2 * j]), p1 = ex2(s[4 * j + 1] - t[2 * j + 1]);
                const float p2 = ex2(s[4 * j + 2] - t[2 * j]), p3 = ex2(s[4 * j + 3] - t[2 * j + 1]);
                pk[2 * j] = pack2(p0, p1);
                pk[2 * j + 1] = pack2(p2, p3);
                s[2 * j] = p0 + p2;
                s[2 * j + 1] = p1 + p3;
            }
#pragma unroll
            for (int jj = 0; jj < 2; jj++) {
                const int mi = lane >> 3, rr = lane & 7;
                const uint32_t a = sb + SM_P + wg * 4096 + (8 * (2 * jj + (mi >> 1)) + rr) * 128 + (((2 * w4 + (mi & 1)) ^ rr) << 4);
                asm volatile("stmatrix.sync.aligned.m8n8.x4.trans.shared.b16 [%0],{%1,%2,%3,%4};" ::"r"(a), "r"(pk[4 * jj]), "r"(pk[4 * jj + 1]), "r"(pk[4 * jj + 2]), "r"(pk[4 * jj + 3]) : "memory");
            }
            fence_async();
            if (r) {
#pragma unroll
                for (int i = 0; i < 8; i++) {
                    const float al = ex2(mo[i] - t[i]);
                    lsum[i] = lsum[i] * al + s[i];
                    o0[4 * (i >> 1) + (i & 1)] *= al; o0[4 * (i >> 1) + 2 + (i & 1)] *= al;
                    o1[4 * (i >> 1) + (i & 1)] *= al; o1[4 * (i >> 1) + 2 + (i & 1)] *= al;
                }
            } else {
#pragma unroll
                for (int i = 0; i < 8; i++) { lsum[i] = s[i]; mo[i] = t[i]; }
            }
            TS(39 + 6 * r);
            bar_sync(1, 256);
            wg_fence();
            const uint32_t dv = mkdesc(SM_C + r * 65536 + wg * 16384), dp = mkdesc(SM_P);
#pragma unroll
            for (int kk = 0; kk < 8; kk++) {
                wgmma_n32<1>(o0, dv + (kk >> 2) * 2048 + (kk & 3) * 128, dp + (kk >> 2) * 256 + (kk & 3) * 2, 1);
                wgmma_n32<1>(o1, dv + (kk >> 2) * 2048 + 512 + (kk & 3) * 128, dp + (kk >> 2) * 256 + (kk & 3) * 2, 1);
            }
            wg_commit();
            TS(7 + r);
        }
        {
            const bool u16 = lane & 16, u8 = lane & 8, u4 = lane & 4;
            float k4[4], k2[2];
#pragma unroll
            for (int i = 0; i < 4; i++) k4[i] = (u16 ? lsum[4 + i] : lsum[i]) + shx(u16 ? lsum[i] : lsum[4 + i], 16);
#pragma unroll
            for (int i = 0; i < 2; i++) k2[i] = (u8 ? k4[2 + i] : k4[i]) + shx(u8 ? k4[i] : k4[2 + i], 8);
            const float k1 = (u4 ? k2[1] : k2[0]) + shx(u4 ? k2[0] : k2[1], 4);
            mbar_wait_w(bars + 8 * BAR_Z2);
            sts32(sb + SM_LS + (q * 8 + g) * 48 + warp * 4, __float_as_uint(k1));
        }
        bar_sync(1, 256);
        float l8[8];
        {
            const float l = sum4(lds128(sb + SM_LS + lane * 48)) + sum4(lds128(sb + SM_LS + lane * 48 + 16));
            if (rk == 0 && warp == 4)
                st1(scr + OFF_ML + (32 * bat + 8 * ((lane & 7) >> 1) + 2 * (lane >> 3) + (lane & 1)) * (32 * MLS) + (cl & 31) * MLS, canonf(mslot + __log2f(l)));
            const float il = __fdividef(1.f, l);
#pragma unroll
            for (int i = 0; i < 8; i++) l8[i] = __shfl_sync(0xffffffffu, il, q * 8 + i);
        }
        TS(40);
        wg_wait0();
        if (lane == 0) mbar_arrive(bars + 8 * (BAR_FREEC + 1));
        TS(41);
        unsigned char* ob = scr + OFF_OB + ((2 * q * 4 + 2 * rk + wg) * 64 + cl) * 256 + (w4 * 8 + g) * 8;
#pragma unroll
        for (int j = 0; j < 4; j++) {
#pragma unroll
            for (int e = 0; e < 2; e++) {
                const float il = l8[2 * j + e];
                stv2(ob + (8 * j + e) * 4 * 16384, canon(pack2(o0[4 * j + e] * il, o0[4 * j + 2 + e] * il)), canon(pack2(o1[4 * j + e] * il, o1[4 * j + 2 + e] * il)));
            }
        }
    }
    TS(11);
    {
        const int bb = warp >> 2, hw = lane >> 4, vv = lane & 15;
        const int r0 = 8 * (warp & 3) + hw;
        uint4 v[4];
        const unsigned char* src = scr + OFF_OB + (cta * 64 + 32 * bb + r0) * 256 + vv * 16;
#pragma unroll
        for (int i = 25; i < 29; i++) mbar_wait_w(bars + 8 * i);
        load_a_t(af, sb + SM_A, warp, lane);
        delay<D4>();
        const unsigned char* ml = scr + OFF_ML + (32 * bb + h) * (32 * MLS) + lane * MLS;
        uint32_t lw = ld1(ml);
        {
            int it = 0;
            while (__any_sync(0xffffffffu, lw == 0u)) { if (++it > SPIN_LIMIT) __trap(); lw = ld1(ml); }
        }
        delay<D4B>();
#pragma unroll
        for (int i = 0; i < 4; i++) v[i] = ldw4(src + i * 512);
        TS(42);
        const int ord = (int)lw ^ (((int)lw >> 31) & 0x7fffffff);
        const int mo = __reduce_max_sync(0xffffffffu, ord);
        const float wgt = ex2(__uint_as_float(lw) - __int_as_float(mo ^ ((mo >> 31) & 0x7fffffff)));
        float w4v[4];
#pragma unroll
        for (int i = 0; i < 4; i++) w4v[i] = __shfl_sync(0xffffffffu, wgt, r0 + 2 * i);
        float z = wgt;
#pragma unroll
        for (int m = 16; m >= 1; m >>= 1) z += shx(z, m);
        z = __fdividef(1.f, z);
        {
            int it = 0;
            while (!(ok4(v[0]) && ok4(v[1]) && ok4(v[2]) && ok4(v[3]))) {
                if (++it > SPIN_LIMIT) __trap();
#pragma unroll
                for (int i = 0; i < 4; i++)
                    if (!ok4(v[i])) v[i] = ldv4(src + i * 512);
            }
        }
        __syncwarp();
        float acc[8];
#pragma unroll
        for (int i = 0; i < 8; i++) acc[i] = 0.f;
#pragma unroll
        for (int i = 0; i < 4; i++) {
            const float w = w4v[i] * z;
            acc[0] += w * bflo(v[i].x); acc[2] += w * bfhi(v[i].x);
            acc[4] += w * bflo(v[i].y); acc[6] += w * bfhi(v[i].y);
            acc[1] += w * bflo(v[i].z); acc[3] += w * bfhi(v[i].z);
            acc[5] += w * bflo(v[i].w); acc[7] += w * bfhi(v[i].w);
        }
        float k4[4];
#pragma unroll
        for (int i = 0; i < 4; i++) k4[i] = (hw ? acc[4 + i] : acc[i]) + shx(hw ? acc[i] : acc[4 + i], 16);
        const int col = 2 * (warp & 3) + bb;
        sts64(act + (col * 4 + (vv & 3)) * 80 + ((vv >> 2) + 4 * hw) * 8, pack2(k4[0], k4[1]), pack2(k4[2], k4[3]));
    }
    TS(12);
    bar_sync(1, 256);
    load_b128<true>(bf, act, lane);
    mma_k128(d, af, bf);
    {
        const bool u2 = lane & 2, u1 = lane & 1;
        const float k0 = (u2 ? d[2] : d[0]) + shx(u2 ? d[0] : d[2], 2);
        const float k1 = (u2 ? d[3] : d[1]) + shx(u2 ? d[1] : d[3], 2);
        const float k = (u1 ? k1 : k0) + shx(u1 ? k0 : k1, 1);
        st1(scr + OFF_CP + h * 4096 + (warp * 4 + sl) * 128 + lane * 4, canonf(k));
    }
    TS(13);
    uint4 mr[3];
    const unsigned char* mrp = scr + OFF_MR + sl * 4096 + tid * 16;
#pragma unroll
    for (int i = 0; i < 3; i++) mr[i] = ldv4(mrp + i * 16384);
#pragma unroll
    for (int i = 31; i < 35; i++) mbar_wait_w(bars + 8 * i);
    load_a_t(af, sb + SM_C + 32768, warp, lane);
    delay<D5>();
    auto mrprep = [&]() {
        pollS<3>(mr, mrp, 16384);
        const int hi = (lane >> 1) & 1, bb = lane & 1;
        const float cb1 = 1.f + sum4(mr[2]);
        const uint32_t a2 = sb + SM_ACT2 + (bb * 4 + (g >> 1)) * 80 + warp * 8 + ((g & 1) + 2 * hi) * 2;
        unsigned short xh;
        asm volatile("ld.shared.u16 %0,[%1];" : "=h"(xh) : "r"(sb + SM_XS + bb * 1024 + (sl * 128 + 16 * warp + g + 8 * hi) * 2) : "memory");
        sts16(a2, __uint_as_float((uint32_t)xh << 16) * cb1);
        sts16(a2 + 8 * 80, cb1);
        sts16(a2 + 16 * 80, sum4(mr[1]));
        const float ga = sum4(mr[0]);
        sts32(sb + SM_GU + 1024 + tid * 4, __float_as_uint(ga * cb1));
        sts32(sb + SM_GU + 2048 + tid * 4, __float_as_uint(ga));
    };
    gather4(scr + OFF_CP + h * 4096, sb + SM_ACTB, tid, warp, lane, []() {});
    TS(14);
    bar_sync(1, 256);
    load_b128<false>(bf, sb + SM_ACTB, lane);
    mma_k128(d, af, bf);
    if (q == 0) stv2(scr + OFF_AP + (sl * 32 + h) * 512 + warp * 64 + g * 8, canon(pack2(d[0], d[1])), canon(pack2(d[2], d[3])));
    if (warp == 0) asm volatile("bar.arrive 5, 64;" ::: "memory");
    TS(15);
    if (cta >= NFF) return;
    mrprep();
    TS(40);
    bar_sync(1, 256);
    TS(33);
    {
        const int hh = lane >> 4, ks = 4 * (warp & 1) + ((lane >> 2) & 3);
        unsigned char* gp = scr + OFF_GP + (4 * h + (warp & 3)) * 4096 + (warp >> 2) * 512 + sl * 4;
        float gc[4];
#pragma unroll
        for (int m = 0; m < 4; m++) gc[m] = __uint_as_float(lds32(sb + SM_GU + 1024 + (32 * ks + 8 * q + 4 * (m >> 1) + 2 * (m & 1) + hh) * 4));
#pragma unroll
        for (int i = 35; i < 39; i++) mbar_wait_w(bars + 8 * i);
        TS(35);
        uint4 v[4];
        const unsigned char* src = scr + OFF_AP + (sl * 32 + 8 * (warp >> 1) + 4 * hh) * 512 + (warp & 1) * 256 + (lane & 15) * 16;
        delay<APE>();
#pragma unroll
        for (int i = 0; i < 4; i++) v[i] = ldv4(src + i * 512);
        load_a_t(af, sb + SM_C + 65536, warp, lane);
        load_b128<true>(bf, sb + SM_ACT2, lane);
        mma_k128(d, af, bf);
        if (q == 1 || q == 2) {
#pragma unroll
            for (int i = 0; i < 4; i++) st1(gp + q * 1024 + (2 * g + (i & 1) + 16 * (i >> 1)) * 16, canonf(d[i]));
        }
        float d0[4];
#pragma unroll
        for (int i = 0; i < 4; i++) d0[i] = q == 0 ? d[i] : 0.f;
        TS(9);
        pollU<4>(v, src, 512);
        float a[8];
        a[0] = (bflo(v[0].x) + bflo(v[1].x)) + (bflo(v[2].x) + bflo(v[3].x)); a[1] = (bfhi(v[0].x) + bfhi(v[1].x)) + (bfhi(v[2].x) + bfhi(v[3].x));
        a[2] = (bflo(v[0].y) + bflo(v[1].y)) + (bflo(v[2].y) + bflo(v[3].y)); a[3] = (bfhi(v[0].y) + bfhi(v[1].y)) + (bfhi(v[2].y) + bfhi(v[3].y));
        a[4] = (bflo(v[0].z) + bflo(v[1].z)) + (bflo(v[2].z) + bflo(v[3].z)); a[5] = (bfhi(v[0].z) + bfhi(v[1].z)) + (bfhi(v[2].z) + bfhi(v[3].z));
        a[6] = (bflo(v[0].w) + bflo(v[1].w)) + (bflo(v[2].w) + bflo(v[3].w)); a[7] = (bfhi(v[0].w) + bfhi(v[1].w)) + (bfhi(v[2].w) + bfhi(v[3].w));
        float k4[4];
#pragma unroll
        for (int m = 0; m < 4; m++) k4[m] = (hh ? a[2 * m + 1] : a[2 * m]) + shx(hh ? a[2 * m] : a[2 * m + 1], 16);
        sts64(sb + SM_RED + (((warp >> 1) * 2 + hh) * 4 + q) * 80 + ks * 8, pack2(k4[0] * gc[0], k4[2] * gc[2]), pack2(k4[1] * gc[1], k4[3] * gc[3]));
        sts128(sb + SM_RED + 4096 + warp * 512 + lane * 16, make_uint4(__float_as_uint(k4[0]), __float_as_uint(k4[1]), __float_as_uint(k4[2]), __float_as_uint(k4[3])));
        TS(16);
        bar_sync(10, 288);
        load_b128<true>(bf, sb + SM_RED, lane);
        mma_k128(d, af, bf);
#pragma unroll
        for (int i = 0; i < 4; i++) d[i] += d0[i];
        const bool u2 = lane & 2, u1 = lane & 1;
        const float k0 = (u2 ? d[2] : d[0]) + shx(u2 ? d[0] : d[2], 2);
        const float k1 = (u2 ? d[3] : d[1]) + shx(u2 ? d[1] : d[3], 2);
        const float k = (u1 ? k1 : k0) + shx(u1 ? k0 : k1, 1);
        st1(gp + (2 * g + (lane & 1) + 8 * (lane & 2)) * 16, canonf(k));
        TS(17);
    }
    {
        uint4 v[4], w[4];
        const unsigned char* src = scr + OFF_GP + cta * 4096 + lane * 16;
        const unsigned char* sts_ = scr + OFF_GP + cta * 4096 + 3072 + (lane & 1) * 16;
#pragma unroll
        for (int i = 0; i < 4; i++) w[i] = ldv4(src + 1024 + i * 512);
        mbar_wait_w(bars + 8 * 39);
        mbar_wait_w(bars + 8 * 40);
        {
            const int kr = (lane & 7) + 8 * (lane >> 4);
#pragma unroll
            for (int s = 0; s < 4; s++)
                ldsm4t(af[s], sb + SM_C + 16384 + warp * 2048 + kr * 128 + (((2 * s + ((lane >> 3) & 1)) ^ (kr & 7)) << 4));
        }
        pollS<4>(w, src + 1024, 512);
        const float p2g = sum4(w[0]), p2u = sum4(w[1]), p3g = sum4(w[2]), p3u = sum4(w[3]);
        delay<D7>();
        for (int it = 0;; it++) {
            v[0] = ldv4(src); v[1] = ldv4(src + 512); v[2] = ldv4(sts_); v[3] = ldv4(sts_ + 32);
            if (__all_sync(0xffffffffu, ok4(v[0]) && ok4(v[1]) && ok4(v[2]) && ok4(v[3]))) break;
            if (it > SPIN_LIMIT) __trap();
        }
        TS(19);
        const float mu = sum4(v[2]) * (1.f / 512.f);
        const float rs = rsqrtf(fmaxf(sum4(v[3]) * (1.f / 512.f) - mu * mu, 0.f) + 1e-5f);
        const float gs = rs * (sum4(v[0]) - mu * p2g) + p3g, us = rs * (sum4(v[1]) - mu * p2u) + p3u;
        const float z = 0.7978845608028654f * (gs + 0.044715f * gs * gs * gs);
        const float th = 1.f - __fdividef(2.f, __expf(2.f * z) + 1.f);
        const float av = 0.5f * gs * (1.f + th) * us;
        const int s0 = 4 * q + (g & 1);
        const float f0 = __shfl_sync(0xffffffffu, av, s0), f1 = __shfl_sync(0xffffffffu, av, s0 + 2);
        const float f2 = __shfl_sync(0xffffffffu, av, s0 + 16), f3 = __shfl_sync(0xffffffffu, av, s0 + 18);
        const uint32_t b0 = lane < 8 ? pack2(f0, f1) : 0u, b1 = lane < 8 ? pack2(f2, f3) : 0u;
#pragma unroll
        for (int s = 0; s < 4; s++) {
            float dd[4] = {0.f, 0.f, 0.f, 0.f};
            mma16816(dd, af[s], b0, b1);
            if (q == 0) stv4(scr + OFF_FP + ((4 * warp + s) * 4 + (g >> 1)) * (NFF * 32) + cta * 32 + (g & 1) * 16, canonf(dd[0]), canonf(dd[1]), canonf(dd[2]), canonf(dd[3]));
        }
        if (warp == 0) asm volatile("bar.arrive 6, 64;" ::: "memory");
        TS(18);
    }
}

typedef CUresult (*PFN_encodeTiled)(CUtensorMap*, CUtensorMapDataType, cuuint32_t, void*, const cuuint64_t*, const cuuint64_t*, const cuuint32_t*,
                                    const cuuint32_t*, CUtensorMapInterleave, CUtensorMapSwizzle, CUtensorMapL2promotion, CUtensorMapFloatOOBfill);

static void enc2d(PFN_encodeTiled fn, CUtensorMap* m, const void* ptr, uint64_t cols, uint64_t rows, uint32_t bc, uint32_t br, CUtensorMapSwizzle sw, int promo = PRW) {
    cuuint64_t dims[2] = {cols, rows}, strides[1] = {cols * 2};
    cuuint32_t box[2] = {bc, br}, es[2] = {1, 1};
    fn(m, CU_TENSOR_MAP_DATA_TYPE_BFLOAT16, 2, const_cast<void*>(ptr), dims, strides, box, es, CU_TENSOR_MAP_INTERLEAVE_NONE, sw,
       (CUtensorMapL2promotion)promo, CU_TENSOR_MAP_FLOAT_OOB_FILL_NONE);
}

extern "C" void kernel_launch(void* const* d_in, const int* in_sizes, int n_in, void* d_out, int out_size) {
    static PFN_encodeTiled fn = nullptr;
    if (!fn) {
        void* f = nullptr;
        cudaDriverEntryPointQueryResult qr;
        cudaGetDriverEntryPoint("cuTensorMapEncodeTiled", &f, cudaEnableDefault, &qr);
        fn = (PFN_encodeTiled)f;
        cudaFuncSetAttribute(fused_kernel, cudaFuncAttributeMaxDynamicSharedMemorySize, SMEM_BYTES);
    }
    Params p;
    enc2d(fn, &p.mod128, d_in[11], 3072, 512, 64, 64, CU_TENSOR_MAP_SWIZZLE_128B);
    enc2d(fn, &p.wq, d_in[2], 4096, 512, 64, 64, CU_TENSOR_MAP_SWIZZLE_128B);
    enc2d(fn, &p.wuk, d_in[3], 4096, 512, 64, 64, CU_TENSOR_MAP_SWIZZLE_128B);
    enc2d(fn, &p.wuv, d_in[4], 4096, 512, 64, 64, CU_TENSOR_MAP_SWIZZLE_128B);
    enc2d(fn, &p.wo, d_in[5], 512, 4096, 64, 64, CU_TENSOR_MAP_SWIZZLE_128B);
    enc2d(fn, &p.ckv, d_in[1], 512, 16384, 64, 64, CU_TENSOR_MAP_SWIZZLE_128B, PRK);
    enc2d(fn, &p.gate, d_in[7], 1792, 512, 64, 64, CU_TENSOR_MAP_SWIZZLE_128B);
    enc2d(fn, &p.up, d_in[8], 1792, 512, 64, 64, CU_TENSOR_MAP_SWIZZLE_128B);
    {
        cuuint64_t dims[3] = {64, 1792, 8}, strides[2] = {1024, 128};
        cuuint32_t box[3] = {64, 16, 4}, es[3] = {1, 1, 1};
        fn(&p.down, CU_TENSOR_MAP_DATA_TYPE_BFLOAT16, 3, d_in[9], dims, strides, box, es, CU_TENSOR_MAP_INTERLEAVE_NONE, CU_TENSOR_MAP_SWIZZLE_128B,
           CU_TENSOR_MAP_L2_PROMOTION_L2_128B, CU_TENSOR_MAP_FLOAT_OOB_FILL_NONE);
    }
    p.x = (const __nv_bfloat16*)d_in[0];
    p.c = (const __nv_bfloat16*)d_in[10];
    p.wmod = (const __nv_bfloat16*)d_in[11];
    p.out = (__nv_bfloat16*)d_out;
    fused_kernel<<<NCTA, 320, SMEM_BYTES>>>(p);
}
```
